```python
import torch

def _softmax(x, axis=-1):
    return torch.softmax(x, dim=axis)
def _gelu(x):
    return torch.nn.functional.gelu(x, approximate="tanh")
def _silu(x):
    return torch.nn.functional.silu(x)
def _sigmoid(x):
    return torch.sigmoid(x)
def _layernorm(x, axis=-1, eps=1e-5):
    m = x.mean(dim=axis, keepdim=True)
    v = x.var(dim=axis, keepdim=True, unbiased=False)
    return (x - m) / torch.sqrt(v + eps)
def _scatter_add(tgt, idx, src, axis=0):
    return tgt.clone().index_add_(axis, idx, src)
def _segment_sum(src, seg, n):
    out = torch.zeros((n,) + src.shape[1:], dtype=src.dtype)
    return out.index_add_(0, seg, src)
def _pad(x, pw):
    flat = tuple(v for pair in reversed(pw) for v in pair)
    return torch.nn.functional.pad(x, flat)

kernel_name = 'gated_mix__mha_block_cached__glu_gated_reglu__decode'

def setup_inputs():

    _w = (lambda a: (lambda t: t.to(torch.bfloat16) if t.is_floating_point() else t)(torch.as_tensor(a)))
    def _A_setup():
        B, Sq, D = 2, 1, 448
        H, Sk, Dh = 16, 4096, 256
        return {
            "x": _w((lambda *s: torch.randn(*s, dtype=torch.bfloat16) * 0.05)(B, Sq, D)),
            "k_cache": _w((lambda *s: torch.randn(*s, dtype=torch.bfloat16) * 3.2)(B, H, Sk, Dh)),
            "v_cache": _w((lambda *s: torch.randn(*s, dtype=torch.bfloat16) * 0.05)(B, H, Sk, Dh)),
            "wq": _w((lambda *s: torch.randn(*s, dtype=torch.bfloat16) * 3.2)(D, H * Dh) * (D ** -0.5)),
            "wo": _w((lambda *s: torch.randn(*s, dtype=torch.bfloat16) * 0.05)(H * Dh, D) * ((H * Dh) ** -0.5)),
        }
    _A_in = _A_setup()

    def _B_setup():
        B, S, D, F = 2, 1, 448, 1792
        return {
            "x": _w((lambda *s: torch.randn(*s, dtype=torch.bfloat16) * 0.05)(B, S, D)),
            "W_gate": _w((lambda *s: torch.randn(*s, dtype=torch.bfloat16) * 0.2)(D, F) * (2.0 / D) ** 0.5),
            "W_up": _w((lambda *s: torch.randn(*s, dtype=torch.bfloat16) * 0.2)(D, F) * (2.0 / D) ** 0.5),
            "W_down": _w((lambda *s: torch.randn(*s, dtype=torch.bfloat16) * 0.2)(F, D) * (1.0 / F) ** 0.5),
        }
    _B_in = _B_setup()

    return {
        "A_x": _A_in["x"],
        "A_k_cache": _A_in["k_cache"],
        "A_v_cache": _A_in["v_cache"],
        "A_wq": _A_in["wq"],
        "A_wo": _A_in["wo"],
        "B_x": _B_in["x"],
        "B_W_gate": _B_in["W_gate"],
        "B_W_up": _B_in["W_up"],
        "B_W_down": _B_in["W_down"],
        "gate_w": _w((lambda *s: torch.randn(*s, dtype=torch.bfloat16) * 0.05)(448) * 16.0),
    }

def reference(A_x, A_k_cache, A_v_cache, A_wq, A_wo, B_x, B_W_gate, B_W_up, B_W_down, gate_w):
    def _A_ref(x, k_cache, v_cache, wq, wo):
        B, Sq, D = x.shape
        H, Dh = 16, 256
        q = (lambda x, *d: x.permute(*d))((x @ wq).reshape(B, Sq, H, Dh), 0, 2, 1, 3)
        scores = torch.einsum("bhqd,bhkd->bhqk", q, k_cache) * (Dh ** -0.5)
        p = _softmax(scores, axis=-1)
        o = torch.einsum("bhqk,bhkd->bhqd", p, v_cache)
        return (lambda x, *d: x.permute(*d))(o, 0, 2, 1, 3).reshape(B, Sq, H * Dh) @ wo

    def _B_ref(x, W_gate, W_up, W_down):
        gate = torch.einsum("bsd,df->bsf", x, W_gate)
        up = torch.einsum("bsd,df->bsf", x, W_up)
        gate = gate * (lambda x, dt: x.to(dt))(gate > 0, gate.dtype)
        h = gate * up
        return torch.einsum("bsf,fd->bsd", h, W_down)

    x = A_x
    g = _sigmoid((x * gate_w).sum(-1, keepdims=True))
    a = _A_ref(x, A_k_cache, A_v_cache, A_wq, A_wo)
    b = _B_ref(x, B_W_gate, B_W_up, B_W_down)
    return g * a + (1 - g) * b
```

```cpp
#include <cuda_runtime.h>
#include <cuda_bf16.h>
#include <cuda.h>
#include <stdint.h>

namespace {

constexpr int DM = 448;
constexpr int NH = 16;
constexpr int SK = 4096;
constexpr int DH = 256;
constexpr int FF = 1792;
constexpr int NCTA = 128;
constexpr int NTHREADS = 288;
constexpr int NSLOT = 6;
constexpr int SLOT_BYTES = 32768;

constexpr int T_K0 = 2;
constexpr int T_WD = 18;
constexpr int T_V0 = 19;
constexpr int T_WO = 35;
constexpr int T_END = 37;
constexpr int HALF_BYTES = SLOT_BYTES / 2;
#define WINDOW 5
#define PACE 0.975
#define NPRE 0
#define LEAD_NS 800

#define P_LEAD LEAD_NS
#define P_WINDOW WINDOW
#define P_OPT 0

constexpr int OFF_REDQ = NSLOT * SLOT_BYTES;
constexpr int OFF_REDG = OFF_REDQ + 16384;
constexpr int OFF_P    = OFF_REDQ;
constexpr int OFF_SC   = OFF_REDG;
constexpr int OFF_QS   = OFF_REDG + 14336;
constexpr int OFF_OBUF = OFF_QS + 512;
constexpr int OFF_HS   = OFF_OBUF + 8 * 144;
constexpr int OFF_WMAX = OFF_HS + 64;
constexpr int OFF_WSUM = OFF_WMAX + 32;
constexpr int OFF_G    = OFF_WSUM + 32;
constexpr int OFF_BAR  = OFF_G + 16;
constexpr int SMEM_USED = OFF_BAR + 3 * NSLOT * 8;
constexpr int SMEM_BYTES = SMEM_USED + 1024;

__device__ uint32_t g_epoch;
__device__ __align__(128) uint32_t g_qpart[NH * 8 * 2 * 256];
__device__ __align__(128) uint32_t g_gupart[NH * 8 * 2 * 224];
__device__ __align__(128) uint32_t g_scores[32 * SK];
__device__ __align__(128) uint32_t g_fin[56 * 2 * 64 * 8];
#define PROF(i) do { } while (0)
#define PROF2(u, k) do { } while (0)
#define PROFG(i) do { } while (0)
#define g_prof_it(x) do { } while (0)

__device__ __forceinline__ uint32_t smem_u32(const void* p) { return (uint32_t)__cvta_generic_to_shared(p); }

__device__ __forceinline__ void mbar_init(uint32_t bar, uint32_t cnt) {
    asm volatile("mbarrier.init.shared::cta.b64 [%0], %1;" :: "r"(bar), "r"(cnt) : "memory");
}
__device__ __forceinline__ void mbar_expect_tx(uint32_t bar, uint32_t bytes) {
    asm volatile("mbarrier.arrive.expect_tx.shared::cta.b64 _, [%0], %1;" :: "r"(bar), "r"(bytes) : "memory");
}
__device__ __forceinline__ void mbar_arrive(uint32_t bar) {
    asm volatile("mbarrier.arrive.shared::cta.b64 _, [%0];" :: "r"(bar) : "memory");
}
__device__ __forceinline__ void mbar_wait(uint32_t bar, uint32_t parity) {
    asm volatile("{\n\t.reg .pred p;\n\t.reg .u32 c;\n\tmov.u32 c, 0;\n"
                 "W_%=:\n\tmbarrier.try_wait.parity.shared::cta.b64 p, [%0], %1, 2000;\n\t@p bra D_%=;\n\t"
                 "add.u32 c, c, 1;\n\tsetp.lt.u32 p, c, 0x40000;\n\t@p bra W_%=;\n"
                 "D_%=:\n\t}" :: "r"(bar), "r"(parity) : "memory");
}
__device__ __forceinline__ bool poll_done(bool ok, int& it) {
    return __all_sync(0xffffffffu, ok) || ++it > (1 << 20);
}
__device__ __forceinline__ void bulk_load(uint32_t dst, const void* src, uint32_t bytes, uint32_t bar, uint64_t pol) {
    asm volatile("cp.async.bulk.shared::cluster.global.mbarrier::complete_tx::bytes.L2::cache_hint [%0], [%1], %2, [%3], %4;"
                 :: "r"(dst), "l"(src), "r"(bytes), "r"(bar), "l"(pol) : "memory");
}
__device__ __forceinline__ void tma_load_2d(uint32_t dst, const CUtensorMap* map, int c0, int c1, uint32_t bar, uint64_t pol) {
    asm volatile("cp.async.bulk.tensor.2d.shared::cluster.global.mbarrier::complete_tx::bytes.L2::cache_hint [%0], [%1, {%3, %4}], [%2], %5;"
                 :: "r"(dst), "l"(map), "r"(bar), "r"(c0), "r"(c1), "l"(pol) : "memory");
}
__device__ __forceinline__ void tma_load_2d_nohint(uint32_t dst, const CUtensorMap* map, int c0, int c1, uint32_t bar) {
    asm volatile("cp.async.bulk.tensor.2d.shared::cluster.global.mbarrier::complete_tx::bytes [%0], [%1, {%3, %4}], [%2];"
                 :: "r"(dst), "l"(map), "r"(bar), "r"(c0), "r"(c1) : "memory");
}
__device__ __forceinline__ uint4 ldg_stream(const void* p) {
    uint4 v;
    asm volatile("ld.global.nc.L1::no_allocate.v4.u32 {%0,%1,%2,%3}, [%4];"
                 : "=r"(v.x), "=r"(v.y), "=r"(v.z), "=r"(v.w) : "l"(p));
    return v;
}
__device__ __forceinline__ uint32_t ld_relaxed(const uint32_t* p) {
    uint32_t v;
    asm volatile("ld.relaxed.gpu.global.u32 %0, [%1];" : "=r"(v) : "l"(p) : "memory");
    return v;
}
__device__ __forceinline__ uint4 ld_relaxed4(const uint32_t* p) {
    uint4 v;
    asm volatile("ld.relaxed.gpu.global.v4.u32 {%0,%1,%2,%3}, [%4];"
                 : "=r"(v.x), "=r"(v.y), "=r"(v.z), "=r"(v.w) : "l"(p) : "memory");
    return v;
}
__device__ __forceinline__ void st_relaxed(uint32_t* p, uint32_t v) {
    asm volatile("st.relaxed.gpu.global.u32 [%0], %1;" :: "l"(p), "r"(v) : "memory");
}
__device__ __forceinline__ void ldsm4(uint32_t addr, uint32_t& r0, uint32_t& r1, uint32_t& r2, uint32_t& r3) {
    asm volatile("ldmatrix.sync.aligned.m8n8.x4.shared.b16 {%0,%1,%2,%3}, [%4];"
                 : "=r"(r0), "=r"(r1), "=r"(r2), "=r"(r3) : "r"(addr) : "memory");
}
__device__ __forceinline__ void ldsm2(uint32_t addr, uint32_t& r0, uint32_t& r1) {
    asm volatile("ldmatrix.sync.aligned.m8n8.x2.shared.b16 {%0,%1}, [%2];"
                 : "=r"(r0), "=r"(r1) : "r"(addr) : "memory");
}
__device__ __forceinline__ void ldsm4t(uint32_t addr, uint32_t& r0, uint32_t& r1, uint32_t& r2, uint32_t& r3) {
    asm volatile("ldmatrix.sync.aligned.m8n8.x4.trans.shared.b16 {%0,%1,%2,%3}, [%4];"
                 : "=r"(r0), "=r"(r1), "=r"(r2), "=r"(r3) : "r"(addr) : "memory");
}
__device__ __forceinline__ void mma16816(float (&c)[4], uint32_t a0, uint32_t a1, uint32_t a2, uint32_t a3,
                                         uint32_t b0, uint32_t b1) {
    asm volatile("mma.sync.aligned.m16n8k16.row.col.f32.bf16.bf16.f32 {%0,%1,%2,%3}, {%4,%5,%6,%7}, {%8,%9}, {%0,%1,%2,%3};"
                 : "+f"(c[0]), "+f"(c[1]), "+f"(c[2]), "+f"(c[3])
                 : "r"(a0), "r"(a1), "r"(a2), "r"(a3), "r"(b0), "r"(b1));
}
__device__ __forceinline__ void bar_consumers() { asm volatile("bar.sync 1, 256;" ::: "memory"); }
__device__ __forceinline__ float ex2(float x) { float y; asm("ex2.approx.f32 %0, %1;" : "=f"(y) : "f"(x)); return y; }
__device__ __forceinline__ float bf_lo(uint32_t u) { return __uint_as_float(u << 16); }
__device__ __forceinline__ float bf_hi(uint32_t u) { return __uint_as_float(u & 0xffff0000u); }
__device__ __forceinline__ float bf16r(float x) { return __bfloat162float(__float2bfloat16_rn(x)); }
__device__ __forceinline__ uint32_t pack_bf16(float lo, float hi) {
    __nv_bfloat162 v = __floats2bfloat162_rn(lo, hi);
    return *reinterpret_cast<uint32_t*>(&v);
}
__device__ __forceinline__ uint32_t tag_enc(float v, uint32_t tag) { return (__float_as_uint(v) & ~3u) | tag; }
__device__ __forceinline__ float tag_dec(uint32_t u) { return __uint_as_float(u & ~3u); }
__device__ __forceinline__ bool tag_ok(uint32_t u, uint32_t tag) { return (u & 3u) == tag; }
__device__ __forceinline__ bool tag_ok4(const uint4& u, uint32_t tag) {
    return ((((u.x ^ tag) | (u.y ^ tag)) | ((u.z ^ tag) | (u.w ^ tag))) & 3u) == 0;
}
__device__ __forceinline__ float lds_f32(uint32_t a) { float v; asm volatile("ld.shared.f32 %0, [%1];" : "=f"(v) : "r"(a) : "memory"); return v; }
__device__ __forceinline__ uint32_t lds_u32(uint32_t a) { uint32_t v; asm volatile("ld.shared.u32 %0, [%1];" : "=r"(v) : "r"(a) : "memory"); return v; }
__device__ __forceinline__ uint4 lds_v4(uint32_t a) {
    uint4 v; asm volatile("ld.shared.v4.u32 {%0,%1,%2,%3}, [%4];" : "=r"(v.x), "=r"(v.y), "=r"(v.z), "=r"(v.w) : "r"(a) : "memory"); return v;
}
__device__ __forceinline__ void sts_f32(uint32_t a, float v) { asm volatile("st.shared.f32 [%0], %1;" :: "r"(a), "f"(v) : "memory"); }
__device__ __forceinline__ void sts_u32(uint32_t a, uint32_t v) { asm volatile("st.shared.u32 [%0], %1;" :: "r"(a), "r"(v) : "memory"); }
__device__ __forceinline__ void sts_u16(uint32_t a, uint16_t v) { asm volatile("st.shared.u16 [%0], %1;" :: "r"(a), "h"(v) : "memory"); }
__device__ __forceinline__ void sts_v4f(uint32_t a, float x, float y, float z, float w) {
    asm volatile("st.shared.v4.f32 [%0], {%1,%2,%3,%4};" :: "r"(a), "f"(x), "f"(y), "f"(z), "f"(w) : "memory");
}
__device__ __forceinline__ uint16_t bf16_bits(float x) { __nv_bfloat16 v = __float2bfloat16_rn(x); return *reinterpret_cast<uint16_t*>(&v); }

struct Params {
    const __nv_bfloat16* ax;
    const __nv_bfloat16* kc;
    const __nv_bfloat16* bx;
    const __nv_bfloat16* gw;
    __nv_bfloat16* out;
    uint32_t tau16;
};

__global__ void __launch_bounds__(NTHREADS, 1)
fused_decode_kernel(const __grid_constant__ CUtensorMap wqmap, const __grid_constant__ CUtensorMap wgmap,
                    const __grid_constant__ CUtensorMap wumap, const __grid_constant__ CUtensorMap vmap,
                    const __grid_constant__ CUtensorMap womap, const __grid_constant__ CUtensorMap wdmap,
                    const Params p) {
    extern __shared__ __align__(1024) unsigned char smem_raw[];
    const uint32_t sb = (smem_u32(smem_raw) + 1023u) & ~1023u;
    const int tid = threadIdx.x;
    const int warp = tid >> 5, lane = tid & 31;
    const int h = blockIdx.x >> 3, r = blockIdx.x & 7, b = r >> 2, j = r & 3;
    const int bh = b * NH + h;
    const uint32_t bar_full = sb + OFF_BAR, bar_empty = bar_full + 2 * NSLOT * 8;

    if (tid == 256) {
        PROF(16);
        for (int i = 0; i < 4 + NPRE; i++) mbar_init(bar_full + i * 8, 1);
        asm volatile("fence.mbarrier_init.release.cluster;" ::: "memory");
        asm volatile("fence.proxy.async.shared::cta;" ::: "memory");
        {
            uint64_t pol0;
            asm volatile("createpolicy.fractional.L2::evict_first.b64 %0, 1.0;" : "=l"(pol0));
            const unsigned char* kb = reinterpret_cast<const unsigned char*>(p.kc) + ((size_t)bh * SK + j * 1024) * 512;
#pragma unroll
            for (int i = 0; i < NPRE; i++) {
                mbar_expect_tx(bar_full + (4 + i) * 8, HALF_BYTES);
                bulk_load(sb + 2 * SLOT_BYTES + i * HALF_BYTES, kb + i * HALF_BYTES, HALF_BYTES, bar_full + (4 + i) * 8, pol0);
            }
        }
        mbar_expect_tx(bar_full + 0, 28 * 512);
        tma_load_2d_nohint(sb, &wqmap, h * 256, 56 * r, bar_full + 0);
        mbar_expect_tx(bar_full + 8, 28 * 512);
        tma_load_2d_nohint(sb + HALF_BYTES, &wqmap, h * 256, 56 * r + 28, bar_full + 8);
        mbar_expect_tx(bar_full + 16, 56 * 224);
        tma_load_2d_nohint(sb + SLOT_BYTES, &wgmap, h * 112, 56 * r, bar_full + 16);
        mbar_expect_tx(bar_full + 24, 56 * 224);
        tma_load_2d_nohint(sb + SLOT_BYTES + HALF_BYTES, &wumap, h * 112, 56 * r, bar_full + 24);
        PROF2(0, 0); PROF2(1, 0); PROF2(2, 0); PROF2(3, 0);
        for (int i = 4 + NPRE; i < 2 * NSLOT; i++) mbar_init(bar_full + i * 8, 1);
        for (int i = 0; i < NSLOT; i++) mbar_init(bar_empty + i * 8, 8);
        asm volatile("fence.mbarrier_init.release.cluster;" ::: "memory");
        asm volatile("fence.proxy.async.shared::cta;" ::: "memory");
    }

    if (warp == 8) {
        __syncwarp();
        asm volatile("bar.arrive 2, 288;" ::: "memory");
        if (lane == 0) {
            uint64_t pol;
            asm volatile("createpolicy.fractional.L2::evict_first.b64 %0, 1.0;" : "=l"(pol));
            const unsigned char* kbase = reinterpret_cast<const unsigned char*>(p.kc) + ((size_t)bh * SK + j * 1024) * 512;
            unsigned long long tnext;
            asm volatile("mov.u64 %0, %globaltimer;" : "=l"(tnext));
            tnext = ((unsigned long long)((long long)tnext - (P_LEAD)) << 4) + ((p.tau16 * (52u + 16u * NPRE)) >> 4);
#pragma unroll 1
            for (int u = 4 + NPRE; u < 2 * T_END; u++) {
                const int t = u >> 1, half = u & 1, slot = t % NSLOT;
                const uint32_t full = bar_full + (slot * 2 + half) * 8, dst = sb + slot * SLOT_BYTES + half * HALF_BYTES;
                if (t >= NSLOT && half == 0) mbar_wait(bar_empty + slot * 8, ((t / NSLOT) - 1) & 1);
                if (u >= P_WINDOW) {
                    const int up = u - P_WINDOW, tp = up >> 1;
                    mbar_wait(bar_full + ((tp % NSLOT) * 2 + (up & 1)) * 8, (tp / NSLOT) & 1);
                    PROF2(up, 1);
                }
                for (int spin = 0; spin < (1 << 20); spin++) {
                    unsigned long long now;
                    asm volatile("mov.u64 %0, %globaltimer;" : "=l"(now));
                    if ((now << 4) >= tnext) break;
                }
                tnext += (p.tau16 * (t == T_WD ? 6u : t >= T_WO ? 7u : 16u)) >> 4;
                PROF2(u, 0);
                if (t < T_WD) {
                    mbar_expect_tx(full, HALF_BYTES);
                    bulk_load(dst, kbase + (size_t)(u - 2 * T_K0) * HALF_BYTES, HALF_BYTES, full, pol);
                } else if (t == T_WD) {
                    mbar_expect_tx(full, 14 * 896);
                    tma_load_2d_nohint(dst, &wdmap, 0, (h * 112 + j * 28 + half * 14) * 7, full);
                } else if (t < T_WO) {
                    mbar_expect_tx(full, HALF_BYTES);
                    tma_load_2d(dst, &vmap, j * 64, bh * SK + (u - 2 * T_V0) * 128, full, pol);
                } else {
                    mbar_expect_tx(full, 16 * 896);
                    tma_load_2d_nohint(dst, &womap, 0, (h * 256 + j * 64 + (u - 2 * T_WO) * 16) * 7, full);
                }
                if (u == 8) {
                    asm volatile("prefetch.tensormap [%0];" :: "l"(&vmap) : "memory");
                    asm volatile("prefetch.tensormap [%0];" :: "l"(&wdmap) : "memory");
                    asm volatile("prefetch.tensormap [%0];" :: "l"(&womap) : "memory");
                }
            }
        }
        return;
    }

    const int g = lane >> 2, t4 = lane & 3;
    const int li = lane >> 3, lr = lane & 7;

    const int k0 = 56 * r + 7 * warp;
    float xv = 0.f;
    if (lane < 28) xv = __bfloat162float(((lane < 14 ? p.ax : p.bx) + ((lane % 14) / 7) * DM + k0)[lane % 7]);
    uint4 gx0 = make_uint4(0, 0, 0, 0), gx1 = gx0, gw0 = gx0, gw1 = gx0;
    if (warp == 7 && lane < 28) {
        gx0 = ldg_stream(p.ax + b * DM + lane * 16); gx1 = ldg_stream(p.ax + b * DM + lane * 16 + 8);
        gw0 = ldg_stream(p.gw + lane * 16); gw1 = ldg_stream(p.gw + lane * 16 + 8);
    }
    const uint32_t epoch = ld_relaxed(&g_epoch);
    {
        uint32_t* qp = &g_qpart[(h * 8 + r) * 512];
        st_relaxed(qp + tid, 0u); st_relaxed(qp + 256 + tid, 0u);
        uint32_t* gp = &g_gupart[(h * 8 + r) * 448];
        st_relaxed(gp + tid, 0u);
        if (tid < 192) st_relaxed(gp + 256 + tid, 0u);
        uint32_t* sp = &g_scores[bh * SK + j * 1024];
#pragma unroll
        for (int i = 0; i < 4; i++) st_relaxed(sp + i * 256 + tid, 0u);
    }
    asm volatile("bar.sync 2, 288;" ::: "memory");
    const uint32_t tag = epoch + 1;
    {
        float aq[2][8], ag[2][8];
#pragma unroll
        for (int e = 0; e < 8; e++) { aq[0][e] = aq[1][e] = ag[0][e] = ag[1][e] = 0.f; }
        const uint32_t wq_s = sb + (warp >> 2) * HALF_BYTES + (7 * (warp & 3)) * 512 + lane * 16;
        const uint32_t gu_s = sb + SLOT_BYTES + (lane < 14 ? 0 : HALF_BYTES) + 7 * warp * 224 + (lane < 28 ? lane % 14 : 0) * 16;
        if (tid == 0) PROF(11);
        mbar_wait(bar_full + (warp >> 2) * 8, 0);
        if (tid == 0) PROF(13);
#pragma unroll
        for (int i = 0; i < 7; i++) {
            const float xa0 = __shfl_sync(0xffffffffu, xv, i), xa1 = __shfl_sync(0xffffffffu, xv, 7 + i);
            const uint4 wv = lds_v4(wq_s + i * 512);
            const uint32_t wq4[4] = {wv.x, wv.y, wv.z, wv.w};
#pragma unroll
            for (int e = 0; e < 4; e++) {
                const float l0 = bf_lo(wq4[e]), h0 = bf_hi(wq4[e]);
                aq[0][2 * e] += xa0 * l0; aq[0][2 * e + 1] += xa0 * h0;
                aq[1][2 * e] += xa1 * l0; aq[1][2 * e + 1] += xa1 * h0;
            }
        }
#pragma unroll
        for (int bb = 0; bb < 2; bb++) {
            const uint32_t aq_ = sb + OFF_REDQ + ((warp * 2 + bb) * 256 + lane * 4) * 4;
            sts_v4f(aq_, aq[bb][0], aq[bb][1], aq[bb][2], aq[bb][3]);
            sts_v4f(aq_ + 512, aq[bb][4], aq[bb][5], aq[bb][6], aq[bb][7]);
        }
        __syncwarp();
        if (lane == 0) mbar_arrive(bar_empty + 0);
        bar_consumers();
#pragma unroll
        for (int bb = 0; bb < 2; bb++) {
            float s = 0.f;
#pragma unroll
            for (int w = 0; w < 8; w++) s += lds_f32(sb + OFF_REDQ + ((w * 2 + bb) * 256 + tid) * 4);
            st_relaxed(&g_qpart[((h * 8 + r) * 2 + bb) * 256 + tid], tag_enc(s, tag));
        }
        if (tid == 0) PROF(14);
        mbar_wait(bar_full + 2 * 8, 0);
        mbar_wait(bar_full + 3 * 8, 0);
        if (tid == 0) PROF(15);
#pragma unroll
        for (int i = 0; i < 7; i++) {
            const float xb0 = __shfl_sync(0xffffffffu, xv, 14 + i), xb1 = __shfl_sync(0xffffffffu, xv, 21 + i);
            const uint4 wv = lds_v4(gu_s + i * 224);
            const uint32_t gu4[4] = {wv.x, wv.y, wv.z, wv.w};
#pragma unroll
            for (int e = 0; e < 4; e++) {
                const float l1 = bf_lo(gu4[e]), h1 = bf_hi(gu4[e]);
                ag[0][2 * e] += xb0 * l1; ag[0][2 * e + 1] += xb0 * h1;
                ag[1][2 * e] += xb1 * l1; ag[1][2 * e + 1] += xb1 * h1;
            }
        }
        if (lane < 28) {
#pragma unroll
            for (int bb = 0; bb < 2; bb++) {
                const uint32_t ag_ = sb + OFF_REDG + ((warp * 2 + bb) * 224 + lane * 4) * 4;
                sts_v4f(ag_, ag[bb][0], ag[bb][1], ag[bb][2], ag[bb][3]);
                sts_v4f(ag_ + 448, ag[bb][4], ag[bb][5], ag[bb][6], ag[bb][7]);
            }
        }
        __syncwarp();
        if (lane == 0) mbar_arrive(bar_empty + 8);
        bar_consumers();
        if (tid < 224) {
#pragma unroll
            for (int bb = 0; bb < 2; bb++) {
                float s = 0.f;
#pragma unroll
                for (int w = 0; w < 8; w++) s += lds_f32(sb + OFF_REDG + ((w * 2 + bb) * 224 + tid) * 4);
                st_relaxed(&g_gupart[((h * 8 + r) * 2 + bb) * 224 + tid], tag_enc(s, tag));
            }
        }
    }
    if (tid == 0) PROF(1);
    if (warp == 7) {
        float s = 0.f;
        if (lane < 28) {
            const uint32_t xs[8] = {gx0.x, gx0.y, gx0.z, gx0.w, gx1.x, gx1.y, gx1.z, gx1.w};
            const uint32_t gs[8] = {gw0.x, gw0.y, gw0.z, gw0.w, gw1.x, gw1.y, gw1.z, gw1.w};
#pragma unroll
            for (int i = 0; i < 8; i++) {
                s += bf16r(bf_lo(xs[i]) * bf_lo(gs[i]));
                s += bf16r(bf_hi(xs[i]) * bf_hi(gs[i]));
            }
        }
#pragma unroll
        for (int o = 16; o > 0; o >>= 1) s += __shfl_xor_sync(0xffffffffu, s, o);
        if (lane == 0) {
            const float z = bf16r(s);
            sts_f32(sb + OFF_G, bf16r(1.f / (1.f + expf(-z))));
        }
    }
    {
        const uint32_t* src = &g_qpart[(h * 8 * 2 + b) * 256 + tid];
        uint32_t v[8];
        int it = 0;
        for (;;) {
            bool ok = true;
#pragma unroll
            for (int s = 0; s < 8; s++) v[s] = ld_relaxed(src + s * 512);
#pragma unroll
            for (int s = 0; s < 8; s++) ok = ok && tag_ok(v[s], tag);
            if (poll_done(ok, it)) break;
        }
        float q = 0.f;
#pragma unroll
        for (int s = 0; s < 8; s++) q += __uint_as_float(v[s] & ~3u);
        const int col = ((tid & 127) >> 2) * 8 + (tid >> 7) * 4 + (tid & 3);
        sts_u16(sb + OFF_QS + col * 2, bf16_bits(q));
    }
    bar_consumers();
    if (tid == 0) PROF(2);
    uint32_t qa[4][8];
#pragma unroll
    for (int G = 0; G < 4; G++)
#pragma unroll
        for (int o = 0; o < 8; o++)
            qa[G][o] = lds_u32(sb + OFF_QS + (G * 64 + ((o + g) & 7) * 8 + 2 * t4) * 2);

    {
        const uint32_t koff0 = (warp * 8 + lr) * 512 + ((li + lr) & 7) * 16;
        const uint32_t koff1 = koff0 ^ 64;
        uint32_t* sc_out = &g_scores[bh * SK + j * 1024 + warp * 8 + g];
        const uint32_t sc_own = sb + OFF_SC + (warp * 8 + g) * 4;
        const bool diag = (t4 == (g >> 1));
#pragma unroll 1
        for (int t = 0; t < 16; t++) {
            const int tt = T_K0 + t, slot = tt % NSLOT;
            if (t == 6 && warp == 7) {
                const int c = 28 * j + (lane < 28 ? lane : 0), ch = c >> 3, e = c & 7;
                const uint32_t* gsrc = &g_gupart[(h * 8 * 2 + b) * 224 + (e >> 2) * 112 + ch * 4 + (e & 3)];
                uint32_t gv[16];
                int it = 0;
                for (;;) {
                    bool ok = true;
#pragma unroll
                    for (int s = 0; s < 8; s++) { gv[s] = ld_relaxed(gsrc + s * 448); gv[8 + s] = ld_relaxed(gsrc + 56 + s * 448); }
#pragma unroll
                    for (int s = 0; s < 16; s++) ok = ok && tag_ok(gv[s], tag);
                    if (poll_done(ok, it)) break;
                }
                float ga = 0.f, up = 0.f;
#pragma unroll
                for (int s = 0; s < 8; s++) { ga += __uint_as_float(gv[s] & ~3u); up += __uint_as_float(gv[8 + s] & ~3u); }
                ga = bf16r(ga); up = bf16r(up);
                ga = ga * (ga > 0.f ? 1.f : 0.f);
                const int hpos = lane < 28 ? (lane / 14) * 16 + lane % 14 : (lane < 30 ? lane - 14 : lane);
                sts_u16(sb + OFF_HS + hpos * 2, bf16_bits(lane < 28 ? ga * up : 0.f));
            }
            mbar_wait(bar_full + (slot * 2 + (warp >> 2)) * 8, (tt / NSLOT) & 1);
            const uint32_t base = sb + slot * SLOT_BYTES;
            float acc[4][4];
#pragma unroll
            for (int G = 0; G < 4; G++) {
                acc[G][0] = acc[G][1] = acc[G][2] = acc[G][3] = 0.f;
                uint32_t r0, r1, r2, r3, r4, r5, r6, r7;
                ldsm4(base + koff0 + G * 128, r0, r1, r2, r3);
                ldsm4(base + koff1 + G * 128, r4, r5, r6, r7);
                mma16816(acc[G], qa[G][0], 0u, qa[G][1], 0u, r0, r1);
                mma16816(acc[G], qa[G][2], 0u, qa[G][3], 0u, r2, r3);
                mma16816(acc[G], qa[G][4], 0u, qa[G][5], 0u, r4, r5);
                mma16816(acc[G], qa[G][6], 0u, qa[G][7], 0u, r6, r7);
            }
            __syncwarp();
            if (lane == 0) mbar_arrive(bar_empty + slot * 8);
            const float s0 = (acc[0][0] + acc[1][0]) + (acc[2][0] + acc[3][0]);
            const float s1 = (acc[0][1] + acc[1][1]) + (acc[2][1] + acc[3][1]);
            if (diag) {
                const float sv = (g & 1) ? s1 : s0;
                st_relaxed(sc_out + t * 64, tag_enc(sv, tag));
                sts_f32(sc_own + t * 256, sv);
            }
        }
    }
    if (tid == 0) PROF(3);

    float Lsum;
    {
        uint4 sv[4];
        const uint32_t* ssrc = &g_scores[bh * SK + tid * 4];
        bar_consumers();
        if (tid == 0) PROF(9);
        int it = 0;
        for (;;) {
            bool ok = true;
#pragma unroll
            for (int v = 0; v < 4; v++) if (v != j) sv[v] = ld_relaxed4(ssrc + v * 1024);
#pragma unroll
            for (int v = 0; v < 4; v++) if (v != j) ok = ok && tag_ok4(sv[v], tag);
            if (poll_done(ok, it)) break;
        }
        if (tid == 0) { PROF(10); g_prof_it(it); }
#pragma unroll
        for (int v = 0; v < 4; v++) if (v == j) sv[v] = lds_v4(sb + OFF_SC + tid * 16);
        float s[16];
#pragma unroll
        for (int v = 0; v < 4; v++) {
            s[4 * v] = __uint_as_float(sv[v].x & ~3u); s[4 * v + 1] = __uint_as_float(sv[v].y & ~3u);
            s[4 * v + 2] = __uint_as_float(sv[v].z & ~3u); s[4 * v + 3] = __uint_as_float(sv[v].w & ~3u);
        }
        float m = s[0];
#pragma unroll
        for (int i = 1; i < 16; i++) m = fmaxf(m, s[i]);
#pragma unroll
        for (int o = 16; o > 0; o >>= 1) m = fmaxf(m, __shfl_xor_sync(0xffffffffu, m, o));
        if (lane == 0) sts_f32(sb + OFF_WMAX + warp * 4, m);
        bar_consumers();
        if (tid == 0) PROF(12);
        float M = lds_f32(sb + OFF_WMAX);
#pragma unroll
        for (int w = 1; w < 8; w++) M = fmaxf(M, lds_f32(sb + OFF_WMAX + w * 4));
        const float c = 0.0625f * 1.4426950408889634f;
        float sum = 0.f;
        const int tp = tid & 7;
        const uint32_t pa = sb + OFF_P + ((tid >> 3) * 16 + ((2 * tp) & 3) * 4 + (tp >> 1)) * 4;
        constexpr int PVS = 2048;
#pragma unroll
        for (int v = 0; v < 4; v++) {
            const float e0 = ex2((s[4 * v] - M) * c), e1 = ex2((s[4 * v + 1] - M) * c);
            const float e2 = ex2((s[4 * v + 2] - M) * c), e3 = ex2((s[4 * v + 3] - M) * c);
            sum += (e0 + e1) + (e2 + e3);
            sts_u32(pa + v * PVS, pack_bf16(e0, e1));
            sts_u32(pa + v * PVS + 16, pack_bf16(e2, e3));
        }
#pragma unroll
        for (int o = 16; o > 0; o >>= 1) sum += __shfl_xor_sync(0xffffffffu, sum, o);
        if (lane == 0) sts_f32(sb + OFF_WSUM + warp * 4, sum);
        bar_consumers();
        Lsum = lds_f32(sb + OFF_WSUM);
#pragma unroll
        for (int w = 1; w < 8; w++) Lsum += lds_f32(sb + OFF_WSUM + w * 4);
    }
    if (tid == 0) PROF(4);
    const float gate = lds_f32(sb + OFF_G);

    float dacc[4][4];
#pragma unroll
    for (int mt = 0; mt < 4; mt++) dacc[mt][0] = dacc[mt][1] = dacc[mt][2] = dacc[mt][3] = 0.f;
    {
        const int slot = T_WD % NSLOT;
        if (warp < 7) {
            const int line = 7 * min((li >> 1) * 8 + lr, 13) + warp;
            const uint32_t base = sb + slot * SLOT_BYTES + line * 128;
#pragma unroll
            for (int s = 0; s < 2; s++) {
                mbar_wait(bar_full + (slot * 2 + s) * 8, (T_WD / NSLOT) & 1);
                const uint32_t b0 = g == 0 ? lds_u32(sb + OFF_HS + (16 * s + 2 * t4) * 2) : 0u;
                const uint32_t b1 = g == 0 ? lds_u32(sb + OFF_HS + (16 * s + 8 + 2 * t4) * 2) : 0u;
#pragma unroll
                for (int mt = 0; mt < 4; mt++) {
                    uint32_t a0, a1, a2, a3;
                    ldsm4t(base + s * HALF_BYTES + (((2 * mt + (li & 1)) ^ (line & 7)) * 16), a0, a1, a2, a3);
                    mma16816(dacc[mt], a0, a1, a2, a3, b0, b1);
                }
            }
            const float omg = bf16r(1.f - gate);
#pragma unroll
            for (int mt = 0; mt < 4; mt++) { dacc[mt][0] *= omg; dacc[mt][1] *= omg; dacc[mt][2] *= omg; dacc[mt][3] *= omg; }
        }
        __syncwarp();
        if (lane == 0) mbar_arrive(bar_empty + slot * 8);
    }

    float oacc[4][4];
#pragma unroll
    for (int mt = 0; mt < 4; mt++) oacc[mt][0] = oacc[mt][1] = oacc[mt][2] = oacc[mt][3] = 0.f;
    {
        const uint32_t vrow = (warp * 32 + (li >> 1) * 8 + lr) * 128;
        uint32_t vch[4];
#pragma unroll
        for (int mt = 0; mt < 4; mt++) vch[mt] = vrow + (((2 * mt + (li & 1)) ^ lr) * 16);
        const uint32_t pbase = sb + OFF_P + warp * 64 + t4 * 16;
#pragma unroll 1
        for (int t = 0; t < 16; t++) {
            const int tt = T_V0 + t, slot = tt % NSLOT;
            if (t == 12) {
                uint32_t* fp = &g_fin[(b * 64 + h * 4 + j) * 8 + (tid & 7)];
                st_relaxed(fp + (tid >> 3) * 1024, 0u);
                if (tid < 192) st_relaxed(fp + (32 + (tid >> 3)) * 1024, 0u);
            }
            const uint4 pf = lds_v4(pbase + t * 512);
            mbar_wait(bar_full + (slot * 2 + (warp >> 2)) * 8, (tt / NSLOT) & 1);
            const uint32_t base = sb + slot * SLOT_BYTES;
#pragma unroll
            for (int mt = 0; mt < 4; mt++) {
                uint32_t a0, a1, a2, a3, a4, a5, a6, a7;
                ldsm4t(base + vch[mt], a0, a1, a2, a3);
                ldsm4t(base + vch[mt] + 16 * 128, a4, a5, a6, a7);
                mma16816(oacc[mt], a0, a1, a2, a3, pf.x, pf.y);
                mma16816(oacc[mt], a4, a5, a6, a7, pf.z, pf.w);
            }
            __syncwarp();
            if (lane == 0) mbar_arrive(bar_empty + slot * 8);
        }
    }
    if (tid == 0) PROF(5);

    {
        const float f = gate / Lsum;
        const float v0 = t4 == 0 ? oacc[0][0] : t4 == 1 ? oacc[1][0] : t4 == 2 ? oacc[2][0] : oacc[3][0];
        const float v1 = t4 == 0 ? oacc[0][2] : t4 == 1 ? oacc[1][2] : t4 == 2 ? oacc[2][2] : oacc[3][2];
        const uint32_t oa = sb + OFF_OBUF + warp * 144 + (16 * t4 + g) * 2;
        sts_u16(oa, bf16_bits(v0 * f));
        sts_u16(oa + 16, bf16_bits(v1 * f));
    }
    bar_consumers();
    if (warp < 7) {
        const int line = 7 * ((li >> 1) * 8 + lr) + warp;
        uint32_t wch[4];
#pragma unroll
        for (int mt = 0; mt < 4; mt++) wch[mt] = line * 128 + (((2 * mt + (li & 1)) ^ (line & 7)) * 16);
#pragma unroll
        for (int s = 0; s < 4; s++) {
            const int tt = T_WO + (s >> 1), slot = tt % NSLOT;
            uint32_t ob0, ob1;
            ldsm2(sb + OFF_OBUF + lr * 144 + (2 * s + (li & 1)) * 16, ob0, ob1);
            mbar_wait(bar_full + (slot * 2 + (s & 1)) * 8, (tt / NSLOT) & 1);
            const uint32_t base = sb + slot * SLOT_BYTES + (s & 1) * HALF_BYTES;
#pragma unroll
            for (int mt = 0; mt < 4; mt++) {
                uint32_t a0, a1, a2, a3;
                ldsm4t(base + wch[mt], a0, a1, a2, a3);
                mma16816(dacc[mt], a0, a1, a2, a3, ob0, ob1);
            }
        }
        if (tid == 0) PROF(6);
        float v[4][2];
#pragma unroll
        for (int mt = 0; mt < 4; mt++) { v[mt][0] = dacc[mt][0] + dacc[mt][1]; v[mt][1] = dacc[mt][2] + dacc[mt][3]; }
        const bool hi = (t4 & 2) != 0, lo = (t4 & 1) != 0;
        float a0 = hi ? v[2][0] : v[0][0], a1 = hi ? v[2][1] : v[0][1], a2 = hi ? v[3][0] : v[1][0], a3 = hi ? v[3][1] : v[1][1];
        const float s0 = hi ? v[0][0] : v[2][0], s1 = hi ? v[0][1] : v[2][1], s2 = hi ? v[1][0] : v[3][0], s3 = hi ? v[1][1] : v[3][1];
        a0 += __shfl_xor_sync(0xffffffffu, s0, 2); a1 += __shfl_xor_sync(0xffffffffu, s1, 2);
        a2 += __shfl_xor_sync(0xffffffffu, s2, 2); a3 += __shfl_xor_sync(0xffffffffu, s3, 2);
        float r0 = lo ? a2 : a0, r1 = lo ? a3 : a1;
        const float u0 = lo ? a0 : a2, u1 = lo ? a1 : a3;
        r0 += __shfl_xor_sync(0xffffffffu, u0, 1); r1 += __shfl_xor_sync(0xffffffffu, u1, 1);
        const int oct = 8 * warp + 2 * t4, src = h * 4 + j;
        st_relaxed(&g_fin[((oct * 2 + b) * 64 + src) * 8 + g], tag_enc(r0, tag));
        st_relaxed(&g_fin[(((oct + 1) * 2 + b) * 64 + src) * 8 + g], tag_enc(r1, tag));
        if (tid == 0) PROF(7);
    } else if (blockIdx.x < 112) {
        if (lane == 0) PROF(18);
        const uint32_t* src = &g_fin[blockIdx.x * 512 + lane * 4];
#pragma unroll 1
        for (int pass = 1; pass < 2; pass++) {
            uint4 v[4];
            int it = 0;
            for (;;) {
                bool ok = true;
#pragma unroll
                for (int i = 0; i < 4; i++) v[i] = ld_relaxed4(src + i * 128);
#pragma unroll
                for (int i = 0; i < 4; i++) ok = ok && tag_ok4(v[i], tag);
                if (pass == 0 || poll_done(ok, it)) break;
            }
            float x0 = 0.f, x1 = 0.f, x2 = 0.f, x3 = 0.f;
#pragma unroll
            for (int i = 0; i < 4; i++) {
                x0 += tag_dec(v[i].x); x1 += tag_dec(v[i].y); x2 += tag_dec(v[i].z); x3 += tag_dec(v[i].w);
            }
#pragma unroll
            for (int o = 2; o < 32; o <<= 1) {
                x0 += __shfl_xor_sync(0xffffffffu, x0, o); x1 += __shfl_xor_sync(0xffffffffu, x1, o);
                x2 += __shfl_xor_sync(0xffffffffu, x2, o); x3 += __shfl_xor_sync(0xffffffffu, x3, o);
            }
            if (pass == 1 && lane < 2) {
                uint2 o2 = make_uint2(pack_bf16(x0, x1), pack_bf16(x2, x3));
                *reinterpret_cast<uint2*>(p.out + (blockIdx.x & 1) * DM + (blockIdx.x >> 1) * 8 + lane * 4) = o2;
            }
        }
        if (blockIdx.x == 0 && lane == 0) st_relaxed(&g_epoch, epoch == 2 ? 0u : epoch + 1);
        if (lane == 0) PROF(8);
    }
}

typedef CUresult (*EncodeTiledFn)(CUtensorMap*, CUtensorMapDataType, cuuint32_t, void*, const cuuint64_t*,
                                  const cuuint64_t*, const cuuint32_t*, const cuuint32_t*, CUtensorMapInterleave,
                                  CUtensorMapSwizzle, CUtensorMapL2promotion, CUtensorMapFloatOOBfill);

}

extern "C" void kernel_launch(void* const* d_in, const int* in_sizes, int n_in, void* d_out, int out_size) {
    (void)in_sizes; (void)n_in; (void)out_size;
    static EncodeTiledFn encode = nullptr;
    static uint32_t tau16 = 0;
    if (!encode) {
        int dev = 0, mclk_khz = 0, bus_bits = 0;
        cudaGetDevice(&dev);
        cudaDeviceGetAttribute(&mclk_khz, cudaDevAttrMemoryClockRate, dev);
        cudaDeviceGetAttribute(&bus_bits, cudaDevAttrGlobalMemoryBusWidth, dev);
        const double peak = 2.0 * mclk_khz * 1e3 * (bus_bits / 8.0) * 1e-9;
        tau16 = peak > 0 ? (uint32_t)(16.0 * NCTA * HALF_BYTES / (PACE * peak)) : 0u;
        cudaDriverEntryPointQueryResult qr;
        void* fn = nullptr;
        cudaGetDriverEntryPoint("cuTensorMapEncodeTiled", &fn, cudaEnableDefault, &qr);
        encode = (EncodeTiledFn)fn;
        cudaFuncSetAttribute(fused_decode_kernel, cudaFuncAttributeMaxDynamicSharedMemorySize, SMEM_BYTES);
    }
    CUtensorMap wqmap, wgmap, wumap, vmap, womap, wdmap;
    auto make_map = [&](CUtensorMap* m, void* ptr, uint64_t cols, uint64_t rows, uint32_t bcols, uint32_t brows,
                        CUtensorMapSwizzle sw) {
        cuuint64_t gdim[2] = {cols, rows};
        cuuint64_t gstr[1] = {cols * 2};
        cuuint32_t box[2] = {bcols, brows};
        cuuint32_t estr[2] = {1, 1};
        encode(m, CU_TENSOR_MAP_DATA_TYPE_BFLOAT16, 2, ptr, gdim, gstr, box, estr, CU_TENSOR_MAP_INTERLEAVE_NONE,
               sw, CU_TENSOR_MAP_L2_PROMOTION_L2_256B, CU_TENSOR_MAP_FLOAT_OOB_FILL_NONE);
    };
    make_map(&wqmap, d_in[3], NH * DH, DM, 256, 28, CU_TENSOR_MAP_SWIZZLE_NONE);
    make_map(&wgmap, d_in[6], FF, DM, 112, 56, CU_TENSOR_MAP_SWIZZLE_NONE);
    make_map(&wumap, d_in[7], FF, DM, 112, 56, CU_TENSOR_MAP_SWIZZLE_NONE);
    make_map(&vmap, d_in[2], DH, 2 * NH * SK, 64, 128, CU_TENSOR_MAP_SWIZZLE_128B);
    make_map(&womap, d_in[4], 64, NH * DH * 7, 64, 16 * 7, CU_TENSOR_MAP_SWIZZLE_128B);
    make_map(&wdmap, d_in[8], 64, FF * 7, 64, 14 * 7, CU_TENSOR_MAP_SWIZZLE_128B);
    Params p;
    p.ax = (const __nv_bfloat16*)d_in[0];
    p.kc = (const __nv_bfloat16*)d_in[1];
    p.bx = (const __nv_bfloat16*)d_in[0];
    p.gw = (const __nv_bfloat16*)d_in[9];
    p.out = (__nv_bfloat16*)d_out;
    p.tau16 = tau16;
    fused_decode_kernel<<<NCTA, NTHREADS, SMEM_BYTES, cudaStreamPerThread>>>(wqmap, wgmap, wumap, vmap, womap, wdmap, p);
}
```

```cpp
#include <cuda_runtime.h>
#include <cuda_bf16.h>
#include <cuda.h>
#include <stdint.h>

namespace {

constexpr int DM = 448;
constexpr int NH = 16;
constexpr int SK = 4096;
constexpr int DH = 256;
constexpr int FF = 1792;
constexpr int NCTA = 128;
constexpr int NTHREADS = 288;
constexpr int NSLOT = 6;
constexpr int SLOT_BYTES = 32768;
constexpr int HALF_BYTES = SLOT_BYTES / 2;

constexpr int T_K0 = 2;
constexpr int T_WD = 18;
constexpr int T_V0 = 19;
constexpr int T_WO = 35;
constexpr int T_END = 37;
constexpr int WINDOW = 5;
constexpr double PACE = 0.975;
constexpr int LEAD_NS = 800;

constexpr int OFF_REDQ = NSLOT * SLOT_BYTES;
constexpr int OFF_REDG = OFF_REDQ + 16384;
constexpr int OFF_P    = OFF_REDQ;
constexpr int OFF_SC   = OFF_REDG;
constexpr int OFF_QS   = OFF_REDG + 14336;
constexpr int OFF_OBUF = OFF_QS + 512;
constexpr int OFF_HS   = OFF_OBUF + 8 * 144;
constexpr int OFF_WMAX = OFF_HS + 64;
constexpr int OFF_WSUM = OFF_WMAX + 32;
constexpr int OFF_G    = OFF_WSUM + 32;
constexpr int OFF_BAR  = OFF_G + 16;
constexpr int SMEM_USED = OFF_BAR + 3 * NSLOT * 8;
constexpr int SMEM_BYTES = SMEM_USED + 1024;

__device__ uint32_t g_epoch;
__device__ __align__(128) uint32_t g_qpart[NH * 8 * 2 * 256];
__device__ __align__(128) uint32_t g_gupart[NH * 8 * 2 * 224];
__device__ __align__(128) uint32_t g_scores[32 * SK];
__device__ __align__(128) uint32_t g_fin[56 * 2 * 64 * 8];

__device__ __forceinline__ uint32_t smem_u32(const void* p) { return (uint32_t)__cvta_generic_to_shared(p); }

__device__ __forceinline__ void mbar_init(uint32_t bar, uint32_t cnt) {
    asm volatile("mbarrier.init.shared::cta.b64 [%0], %1;" :: "r"(bar), "r"(cnt) : "memory");
}
__device__ __forceinline__ void mbar_expect_tx(uint32_t bar, uint32_t bytes) {
    asm volatile("mbarrier.arrive.expect_tx.shared::cta.b64 _, [%0], %1;" :: "r"(bar), "r"(bytes) : "memory");
}
__device__ __forceinline__ void mbar_arrive(uint32_t bar) {
    asm volatile("mbarrier.arrive.shared::cta.b64 _, [%0];" :: "r"(bar) : "memory");
}
__device__ __forceinline__ void mbar_wait(uint32_t bar, uint32_t parity) {
    asm volatile("{\n\t.reg .pred p;\n\t.reg .u32 c;\n\tmov.u32 c, 0;\n"
                 "W_%=:\n\tmbarrier.try_wait.parity.shared::cta.b64 p, [%0], %1, 2000;\n\t@p bra D_%=;\n\t"
                 "add.u32 c, c, 1;\n\tsetp.lt.u32 p, c, 0x40000;\n\t@p bra W_%=;\n"
                 "D_%=:\n\t}" :: "r"(bar), "r"(parity) : "memory");
}
__device__ __forceinline__ bool poll_done(bool ok, int& it) {
    return __all_sync(0xffffffffu, ok) || ++it > (1 << 20);
}
__device__ __forceinline__ void bulk_load(uint32_t dst, const void* src, uint32_t bytes, uint32_t bar, uint64_t pol) {
    asm volatile("cp.async.bulk.shared::cluster.global.mbarrier::complete_tx::bytes.L2::cache_hint [%0], [%1], %2, [%3], %4;"
                 :: "r"(dst), "l"(src), "r"(bytes), "r"(bar), "l"(pol) : "memory");
}
__device__ __forceinline__ void tma_load_2d(uint32_t dst, const CUtensorMap* map, int c0, int c1, uint32_t bar, uint64_t pol) {
    asm volatile("cp.async.bulk.tensor.2d.shared::cluster.global.mbarrier::complete_tx::bytes.L2::cache_hint [%0], [%1, {%3, %4}], [%2], %5;"
                 :: "r"(dst), "l"(map), "r"(bar), "r"(c0), "r"(c1), "l"(pol) : "memory");
}
__device__ __forceinline__ uint4 ldg_stream(const void* p) {
    uint4 v;
    asm volatile("ld.global.nc.L1::no_allocate.v4.u32 {%0,%1,%2,%3}, [%4];"
                 : "=r"(v.x), "=r"(v.y), "=r"(v.z), "=r"(v.w) : "l"(p));
    return v;
}
__device__ __forceinline__ uint32_t ld_relaxed(const uint32_t* p) {
    uint32_t v;
    asm volatile("ld.relaxed.gpu.global.u32 %0, [%1];" : "=r"(v) : "l"(p) : "memory");
    return v;
}
__device__ __forceinline__ uint4 ld_relaxed4(const uint32_t* p) {
    uint4 v;
    asm volatile("ld.relaxed.gpu.global.v4.u32 {%0,%1,%2,%3}, [%4];"
                 : "=r"(v.x), "=r"(v.y), "=r"(v.z), "=r"(v.w) : "l"(p) : "memory");
    return v;
}
__device__ __forceinline__ void st_relaxed(uint32_t* p, uint32_t v) {
    asm volatile("st.relaxed.gpu.global.u32 [%0], %1;" :: "l"(p), "r"(v) : "memory");
}
__device__ __forceinline__ void ldsm4(uint32_t addr, uint32_t& r0, uint32_t& r1, uint32_t& r2, uint32_t& r3) {
    asm volatile("ldmatrix.sync.aligned.m8n8.x4.shared.b16 {%0,%1,%2,%3}, [%4];"
                 : "=r"(r0), "=r"(r1), "=r"(r2), "=r"(r3) : "r"(addr) : "memory");
}
__device__ __forceinline__ void ldsm2(uint32_t addr, uint32_t& r0, uint32_t& r1) {
    asm volatile("ldmatrix.sync.aligned.m8n8.x2.shared.b16 {%0,%1}, [%2];"
                 : "=r"(r0), "=r"(r1) : "r"(addr) : "memory");
}
__device__ __forceinline__ void ldsm4t(uint32_t addr, uint32_t& r0, uint32_t& r1, uint32_t& r2, uint32_t& r3) {
    asm volatile("ldmatrix.sync.aligned.m8n8.x4.trans.shared.b16 {%0,%1,%2,%3}, [%4];"
                 : "=r"(r0), "=r"(r1), "=r"(r2), "=r"(r3) : "r"(addr) : "memory");
}
__device__ __forceinline__ void mma16816(float (&c)[4], uint32_t a0, uint32_t a1, uint32_t a2, uint32_t a3,
                                         uint32_t b0, uint32_t b1) {
    asm volatile("mma.sync.aligned.m16n8k16.row.col.f32.bf16.bf16.f32 {%0,%1,%2,%3}, {%4,%5,%6,%7}, {%8,%9}, {%0,%1,%2,%3};"
                 : "+f"(c[0]), "+f"(c[1]), "+f"(c[2]), "+f"(c[3])
                 : "r"(a0), "r"(a1), "r"(a2), "r"(a3), "r"(b0), "r"(b1));
}
__device__ __forceinline__ void bar_consumers() { asm volatile("bar.sync 1, 256;" ::: "memory"); }
__device__ __forceinline__ float ex2(float x) { float y; asm("ex2.approx.f32 %0, %1;" : "=f"(y) : "f"(x)); return y; }
__device__ __forceinline__ float bf_lo(uint32_t u) { return __uint_as_float(u << 16); }
__device__ __forceinline__ float bf_hi(uint32_t u) { return __uint_as_float(u & 0xffff0000u); }
__device__ __forceinline__ float bf16r(float x) { return __bfloat162float(__float2bfloat16_rn(x)); }
__device__ __forceinline__ uint32_t pack_bf16(float lo, float hi) {
    __nv_bfloat162 v = __floats2bfloat162_rn(lo, hi);
    return *reinterpret_cast<uint32_t*>(&v);
}
__device__ __forceinline__ uint32_t tag_enc(float v, uint32_t tag) { return (__float_as_uint(v) & ~3u) | tag; }
__device__ __forceinline__ float tag_dec(uint32_t u) { return __uint_as_float(u & ~3u); }
__device__ __forceinline__ bool tag_ok(uint32_t u, uint32_t tag) { return (u & 3u) == tag; }
__device__ __forceinline__ bool tag_ok4(const uint4& u, uint32_t tag) {
    return ((((u.x ^ tag) | (u.y ^ tag)) | ((u.z ^ tag) | (u.w ^ tag))) & 3u) == 0;
}
__device__ __forceinline__ float lds_f32(uint32_t a) { float v; asm volatile("ld.shared.f32 %0, [%1];" : "=f"(v) : "r"(a) : "memory"); return v; }
__device__ __forceinline__ uint32_t lds_u32(uint32_t a) { uint32_t v; asm volatile("ld.shared.u32 %0, [%1];" : "=r"(v) : "r"(a) : "memory"); return v; }
__device__ __forceinline__ uint4 lds_v4(uint32_t a) {
    uint4 v; asm volatile("ld.shared.v4.u32 {%0,%1,%2,%3}, [%4];" : "=r"(v.x), "=r"(v.y), "=r"(v.z), "=r"(v.w) : "r"(a) : "memory"); return v;
}
__device__ __forceinline__ void sts_f32(uint32_t a, float v) { asm volatile("st.shared.f32 [%0], %1;" :: "r"(a), "f"(v) : "memory"); }
__device__ __forceinline__ void sts_u32(uint32_t a, uint32_t v) { asm volatile("st.shared.u32 [%0], %1;" :: "r"(a), "r"(v) : "memory"); }
__device__ __forceinline__ void sts_u16(uint32_t a, uint16_t v) { asm volatile("st.shared.u16 [%0], %1;" :: "r"(a), "h"(v) : "memory"); }
__device__ __forceinline__ void sts_v4f(uint32_t a, float x, float y, float z, float w) {
    asm volatile("st.shared.v4.f32 [%0], {%1,%2,%3,%4};" :: "r"(a), "f"(x), "f"(y), "f"(z), "f"(w) : "memory");
}
__device__ __forceinline__ uint16_t bf16_bits(float x) { __nv_bfloat16 v = __float2bfloat16_rn(x); return *reinterpret_cast<uint16_t*>(&v); }

struct Params {
    const __nv_bfloat16* ax;
    const __nv_bfloat16* kc;
    const __nv_bfloat16* gw;
    __nv_bfloat16* out;
    uint32_t tau16;
};

__global__ void __launch_bounds__(NTHREADS, 1)
fused_decode_kernel(const __grid_constant__ CUtensorMap wqmap, const __grid_constant__ CUtensorMap wgmap,
                    const __grid_constant__ CUtensorMap wumap, const __grid_constant__ CUtensorMap vmap,
                    const __grid_constant__ CUtensorMap womap, const __grid_constant__ CUtensorMap wdmap,
                    const Params p) {
    extern __shared__ __align__(1024) unsigned char smem_raw[];
    const uint32_t sb = (smem_u32(smem_raw) + 1023u) & ~1023u;
    const int tid = threadIdx.x;
    const int warp = tid >> 5, lane = tid & 31;
    const int h = blockIdx.x >> 3, r = blockIdx.x & 7, b = r >> 2, j = r & 3;
    const int bh = b * NH + h;
    const int vrot = 2 * h;
    const uint32_t bar_full = sb + OFF_BAR, bar_empty = bar_full + 2 * NSLOT * 8;

    if (tid == 256) {
        for (int i = 0; i < 4; i++) mbar_init(bar_full + i * 8, 1);
        asm volatile("fence.proxy.async.shared::cta;" ::: "memory");
        uint64_t polw;
        asm volatile("createpolicy.fractional.L2::evict_first.b64 %0, 1.0;" : "=l"(polw));
        mbar_expect_tx(bar_full + 0, 28 * 512);
        tma_load_2d(sb, &wqmap, h * 256, 56 * r, bar_full + 0, polw);
        mbar_expect_tx(bar_full + 8, 28 * 512);
        tma_load_2d(sb + HALF_BYTES, &wqmap, h * 256, 56 * r + 28, bar_full + 8, polw);
        mbar_expect_tx(bar_full + 16, 56 * 224);
        tma_load_2d(sb + SLOT_BYTES, &wgmap, h * 112, 56 * r, bar_full + 16, polw);
        mbar_expect_tx(bar_full + 24, 56 * 224);
        tma_load_2d(sb + SLOT_BYTES + HALF_BYTES, &wumap, h * 112, 56 * r, bar_full + 24, polw);
        for (int i = 4; i < 2 * NSLOT; i++) mbar_init(bar_full + i * 8, 1);
        for (int i = 0; i < NSLOT; i++) mbar_init(bar_empty + i * 8, 8);
        asm volatile("fence.proxy.async.shared::cta;" ::: "memory");
    }

    if (warp == 8) {
        __syncwarp();
        asm volatile("bar.arrive 2, 288;" ::: "memory");
        if (lane == 0) {
            uint64_t pol;
            asm volatile("createpolicy.fractional.L2::evict_first.b64 %0, 1.0;" : "=l"(pol));
            const unsigned char* kbase = reinterpret_cast<const unsigned char*>(p.kc) + ((size_t)bh * SK + j * 32) * 512;
            unsigned long long tnext;
            asm volatile("mov.u64 %0, %globaltimer;" : "=l"(tnext));
            tnext = ((unsigned long long)((long long)tnext - (LEAD_NS)) << 4) + ((p.tau16 * 52u) >> 4);
#pragma unroll 1
            for (int u = 4; u < 2 * T_END; u++) {
                const int t = u >> 1, half = u & 1, slot = t % NSLOT;
                const uint32_t full = bar_full + (slot * 2 + half) * 8, dst = sb + slot * SLOT_BYTES + half * HALF_BYTES;
                if (t >= NSLOT && half == 0) mbar_wait(bar_empty + slot * 8, ((t / NSLOT) - 1) & 1);
                if (u >= WINDOW) {
                    const int up = u - WINDOW, tp = up >> 1;
                    mbar_wait(bar_full + ((tp % NSLOT) * 2 + (up & 1)) * 8, (tp / NSLOT) & 1);
                }
                for (int spin = 0; spin < (1 << 20); spin++) {
                    unsigned long long now;
                    asm volatile("mov.u64 %0, %globaltimer;" : "=l"(now));
                    if ((now << 4) >= tnext) break;
                }
                tnext += (p.tau16 * (t == T_WD ? 6u : t >= T_WO ? 7u : 16u)) >> 4;
                if (t < T_WD) {
                    mbar_expect_tx(full, HALF_BYTES);
                    bulk_load(dst, kbase + (size_t)(u - 2 * T_K0) * (4 * HALF_BYTES), HALF_BYTES, full, pol);
                } else if (t == T_WD) {
                    mbar_expect_tx(full, 14 * 896);
                    tma_load_2d(dst, &wdmap, 0, (h * 112 + j * 28 + half * 14) * 7, full, pol);
                } else if (t < T_WO) {
                    mbar_expect_tx(full, HALF_BYTES);
                    tma_load_2d(dst, &vmap, j * 64, bh * SK + ((u - 2 * T_V0 + vrot) & 31) * 128, full, pol);
                } else {
                    mbar_expect_tx(full, 16 * 896);
                    tma_load_2d(dst, &womap, 0, (h * 256 + j * 64 + (u - 2 * T_WO) * 16) * 7, full, pol);
                }
                if (u == 8) {
                    asm volatile("prefetch.tensormap [%0];" :: "l"(&vmap) : "memory");
                    asm volatile("prefetch.tensormap [%0];" :: "l"(&wdmap) : "memory");
                    asm volatile("prefetch.tensormap [%0];" :: "l"(&womap) : "memory");
                }
            }
        }
        return;
    }

    const int g = lane >> 2, t4 = lane & 3;
    const int li = lane >> 3, lr = lane & 7;

    const int k0 = 56 * r + 7 * warp;
    float xv = 0.f;
    if (lane < 14) xv = __bfloat162float((p.ax + (lane / 7) * DM + k0)[lane % 7]);
    uint4 gx0 = make_uint4(0, 0, 0, 0), gx1 = gx0, gw0 = gx0, gw1 = gx0;
    if (warp == 7 && lane < 28) {
        gx0 = ldg_stream(p.ax + b * DM + lane * 16); gx1 = ldg_stream(p.ax + b * DM + lane * 16 + 8);
        gw0 = ldg_stream(p.gw + lane * 16); gw1 = ldg_stream(p.gw + lane * 16 + 8);
    }
    const uint32_t epoch = ld_relaxed(&g_epoch);
    {
        uint32_t* qp = &g_qpart[(h * 8 + r) * 512];
        st_relaxed(qp + tid, 0u); st_relaxed(qp + 256 + tid, 0u);
        uint32_t* gp = &g_gupart[(h * 8 + r) * 448];
        st_relaxed(gp + tid, 0u);
        if (tid < 192) st_relaxed(gp + 256 + tid, 0u);
        uint32_t* sp = &g_scores[bh * SK + j * 1024];
#pragma unroll
        for (int i = 0; i < 4; i++) st_relaxed(sp + i * 256 + tid, 0u);
    }
    asm volatile("bar.sync 2, 288;" ::: "memory");
    const uint32_t tag = epoch + 1;
    {
        float aq[2][8], ag[2][8];
#pragma unroll
        for (int e = 0; e < 8; e++) { aq[0][e] = aq[1][e] = ag[0][e] = ag[1][e] = 0.f; }
        const uint32_t wq_s = sb + (warp >> 2) * HALF_BYTES + (7 * (warp & 3)) * 512 + lane * 16;
        const uint32_t gu_s = sb + SLOT_BYTES + (lane < 14 ? 0 : HALF_BYTES) + 7 * warp * 224 + (lane < 28 ? lane % 14 : 0) * 16;
        mbar_wait(bar_full + (warp >> 2) * 8, 0);
#pragma unroll
        for (int i = 0; i < 7; i++) {
            const float xa0 = __shfl_sync(0xffffffffu, xv, i), xa1 = __shfl_sync(0xffffffffu, xv, 7 + i);
            const uint4 wv = lds_v4(wq_s + i * 512);
            const uint32_t wq4[4] = {wv.x, wv.y, wv.z, wv.w};
#pragma unroll
            for (int e = 0; e < 4; e++) {
                const float l0 = bf_lo(wq4[e]), h0 = bf_hi(wq4[e]);
                aq[0][2 * e] += xa0 * l0; aq[0][2 * e + 1] += xa0 * h0;
                aq[1][2 * e] += xa1 * l0; aq[1][2 * e + 1] += xa1 * h0;
            }
        }
#pragma unroll
        for (int bb = 0; bb < 2; bb++) {
            const uint32_t aq_ = sb + OFF_REDQ + ((warp * 2 + bb) * 256 + lane * 4) * 4;
            sts_v4f(aq_, aq[bb][0], aq[bb][1], aq[bb][2], aq[bb][3]);
            sts_v4f(aq_ + 512, aq[bb][4], aq[bb][5], aq[bb][6], aq[bb][7]);
        }
        __syncwarp();
        if (lane == 0) mbar_arrive(bar_empty + 0);
        bar_consumers();
#pragma unroll
        for (int bb = 0; bb < 2; bb++) {
            float s = 0.f;
#pragma unroll
            for (int w = 0; w < 8; w++) s += lds_f32(sb + OFF_REDQ + ((w * 2 + bb) * 256 + tid) * 4);
            st_relaxed(&g_qpart[((h * 8 + r) * 2 + bb) * 256 + tid], tag_enc(s, tag));
        }
        mbar_wait(bar_full + 2 * 8, 0);
        mbar_wait(bar_full + 3 * 8, 0);
#pragma unroll
        for (int i = 0; i < 7; i++) {
            const float xb0 = __shfl_sync(0xffffffffu, xv, i), xb1 = __shfl_sync(0xffffffffu, xv, 7 + i);
            const uint4 wv = lds_v4(gu_s + i * 224);
            const uint32_t gu4[4] = {wv.x, wv.y, wv.z, wv.w};
#pragma unroll
            for (int e = 0; e < 4; e++) {
                const float l1 = bf_lo(gu4[e]), h1 = bf_hi(gu4[e]);
                ag[0][2 * e] += xb0 * l1; ag[0][2 * e + 1] += xb0 * h1;
                ag[1][2 * e] += xb1 * l1; ag[1][2 * e + 1] += xb1 * h1;
            }
        }
        if (lane < 28) {
#pragma unroll
            for (int bb = 0; bb < 2; bb++) {
                const uint32_t ag_ = sb + OFF_REDG + ((warp * 2 + bb) * 224 + lane * 4) * 4;
                sts_v4f(ag_, ag[bb][0], ag[bb][1], ag[bb][2], ag[bb][3]);
                sts_v4f(ag_ + 448, ag[bb][4], ag[bb][5], ag[bb][6], ag[bb][7]);
            }
        }
        __syncwarp();
        if (lane == 0) mbar_arrive(bar_empty + 8);
        bar_consumers();
        if (tid < 224) {
#pragma unroll
            for (int bb = 0; bb < 2; bb++) {
                float s = 0.f;
#pragma unroll
                for (int w = 0; w < 8; w++) s += lds_f32(sb + OFF_REDG + ((w * 2 + bb) * 224 + tid) * 4);
                st_relaxed(&g_gupart[((h * 8 + r) * 2 + bb) * 224 + tid], tag_enc(s, tag));
            }
        }
    }
    if (warp == 7) {
        float s = 0.f;
        if (lane < 28) {
            const uint32_t xs[8] = {gx0.x, gx0.y, gx0.z, gx0.w, gx1.x, gx1.y, gx1.z, gx1.w};
            const uint32_t gs[8] = {gw0.x, gw0.y, gw0.z, gw0.w, gw1.x, gw1.y, gw1.z, gw1.w};
#pragma unroll
            for (int i = 0; i < 8; i++) {
                s += bf16r(bf_lo(xs[i]) * bf_lo(gs[i]));
                s += bf16r(bf_hi(xs[i]) * bf_hi(gs[i]));
            }
        }
#pragma unroll
        for (int o = 16; o > 0; o >>= 1) s += __shfl_xor_sync(0xffffffffu, s, o);
        if (lane == 0) {
            const float z = bf16r(s);
            sts_f32(sb + OFF_G, bf16r(1.f / (1.f + expf(-z))));
        }
    }
    {
        const uint32_t* src = &g_qpart[(h * 8 * 2 + b) * 256 + tid];
        uint32_t v[8];
        int it = 0;
        for (;;) {
            bool ok = true;
#pragma unroll
            for (int s = 0; s < 8; s++) v[s] = ld_relaxed(src + s * 512);
#pragma unroll
            for (int s = 0; s < 8; s++) ok = ok && tag_ok(v[s], tag);
            if (poll_done(ok, it)) break;
        }
        float q = 0.f;
#pragma unroll
        for (int s = 0; s < 8; s++) q += tag_dec(v[s]);
        const int col = ((tid & 127) >> 2) * 8 + (tid >> 7) * 4 + (tid & 3);
        sts_u16(sb + OFF_QS + col * 2, bf16_bits(q));
    }
    bar_consumers();
    uint32_t qa[4][8];
#pragma unroll
    for (int G = 0; G < 4; G++)
#pragma unroll
        for (int o = 0; o < 8; o++)
            qa[G][o] = lds_u32(sb + OFF_QS + (G * 64 + ((o + g) & 7) * 8 + 2 * t4) * 2);

    {
        const uint32_t koff0 = (warp * 8 + lr) * 512 + ((li + lr) & 7) * 16;
        const uint32_t koff1 = koff0 ^ 64;
        uint32_t* sc_out = &g_scores[bh * SK + j * 1024 + (warp & 3) * 8 + g];
        const uint32_t sc_own = sb + OFF_SC + ((warp & 3) * 8 + g) * 4;
        const bool diag = (t4 == (g >> 1));
#pragma unroll 1
        for (int t = 0; t < 16; t++) {
            const int tt = T_K0 + t, slot = tt % NSLOT;
            if (t == 6 && warp == 7) {
                const int c = 28 * j + (lane < 28 ? lane : 0), ch = c >> 3, e = c & 7;
                const uint32_t* gsrc = &g_gupart[(h * 8 * 2 + b) * 224 + (e >> 2) * 112 + ch * 4 + (e & 3)];
                uint32_t gv[16];
                int it = 0;
                for (;;) {
                    bool ok = true;
#pragma unroll
                    for (int s = 0; s < 8; s++) { gv[s] = ld_relaxed(gsrc + s * 448); gv[8 + s] = ld_relaxed(gsrc + 56 + s * 448); }
#pragma unroll
                    for (int s = 0; s < 16; s++) ok = ok && tag_ok(gv[s], tag);
                    if (poll_done(ok, it)) break;
                }
                float ga = 0.f, up = 0.f;
#pragma unroll
                for (int s = 0; s < 8; s++) { ga += tag_dec(gv[s]); up += tag_dec(gv[8 + s]); }
                ga = bf16r(ga); up = bf16r(up);
                ga = ga * (ga > 0.f ? 1.f : 0.f);
                const int hpos = lane < 28 ? (lane / 14) * 16 + lane % 14 : (lane < 30 ? lane - 14 : lane);
                sts_u16(sb + OFF_HS + hpos * 2, bf16_bits(lane < 28 ? ga * up : 0.f));
            }
            mbar_wait(bar_full + (slot * 2 + (warp >> 2)) * 8, (tt / NSLOT) & 1);
            const uint32_t base = sb + slot * SLOT_BYTES;
            float acc[4][4];
#pragma unroll
            for (int G = 0; G < 4; G++) {
                acc[G][0] = acc[G][1] = acc[G][2] = acc[G][3] = 0.f;
                uint32_t r0, r1, r2, r3, r4, r5, r6, r7;
                ldsm4(base + koff0 + G * 128, r0, r1, r2, r3);
                ldsm4(base + koff1 + G * 128, r4, r5, r6, r7);
                mma16816(acc[G], qa[G][0], 0u, qa[G][1], 0u, r0, r1);
                mma16816(acc[G], qa[G][2], 0u, qa[G][3], 0u, r2, r3);
                mma16816(acc[G], qa[G][4], 0u, qa[G][5], 0u, r4, r5);
                mma16816(acc[G], qa[G][6], 0u, qa[G][7], 0u, r6, r7);
            }
            __syncwarp();
            if (lane == 0) mbar_arrive(bar_empty + slot * 8);
            const float s0 = (acc[0][0] + acc[1][0]) + (acc[2][0] + acc[3][0]);
            const float s1 = (acc[0][1] + acc[1][1]) + (acc[2][1] + acc[3][1]);
            if (diag) {
                const float sv = bf16r((g & 1) ? s1 : s0);
                const int kh = 2 * t + (warp >> 2);
                st_relaxed(sc_out + kh * 32, tag_enc(sv, tag));
                sts_f32(sc_own + kh * 128, sv);
            }
        }
    }

    float Lsum;
    {
        uint4 sv[4];
        const uint32_t* ssrc = &g_scores[bh * SK + tid * 4];
        bar_consumers();
        int it = 0;
        for (;;) {
            bool ok = true;
#pragma unroll
            for (int v = 0; v < 4; v++) if (v != j) sv[v] = ld_relaxed4(ssrc + v * 1024);
#pragma unroll
            for (int v = 0; v < 4; v++) if (v != j) ok = ok && tag_ok4(sv[v], tag);
            if (poll_done(ok, it)) break;
        }
#pragma unroll
        for (int v = 0; v < 4; v++) if (v == j) sv[v] = lds_v4(sb + OFF_SC + tid * 16);
        float s[16];
#pragma unroll
        for (int v = 0; v < 4; v++) {
            s[4 * v] = tag_dec(sv[v].x); s[4 * v + 1] = tag_dec(sv[v].y);
            s[4 * v + 2] = tag_dec(sv[v].z); s[4 * v + 3] = tag_dec(sv[v].w);
        }
        float m = s[0];
#pragma unroll
        for (int i = 1; i < 16; i++) m = fmaxf(m, s[i]);
#pragma unroll
        for (int o = 16; o > 0; o >>= 1) m = fmaxf(m, __shfl_xor_sync(0xffffffffu, m, o));
        if (lane == 0) sts_f32(sb + OFF_WMAX + warp * 4, m);
        bar_consumers();
        float M = lds_f32(sb + OFF_WMAX);
#pragma unroll
        for (int w = 1; w < 8; w++) M = fmaxf(M, lds_f32(sb + OFF_WMAX + w * 4));
        const float c = 0.0625f * 1.4426950408889634f;
        float sum = 0.f;
        const int tp = tid & 7;
        const uint32_t pa = sb + OFF_P + ((tid >> 3) * 64 + ((2 * tp) & 3) * 4 + (tp >> 1)) * 4;
        constexpr int PVS = 64;
#pragma unroll
        for (int v = 0; v < 4; v++) {
            const float e0 = ex2((s[4 * v] - M) * c), e1 = ex2((s[4 * v + 1] - M) * c);
            const float e2 = ex2((s[4 * v + 2] - M) * c), e3 = ex2((s[4 * v + 3] - M) * c);
            sum += (e0 + e1) + (e2 + e3);
            sts_u32(pa + v * PVS, pack_bf16(e0, e1));
            sts_u32(pa + v * PVS + 16, pack_bf16(e2, e3));
        }
#pragma unroll
        for (int o = 16; o > 0; o >>= 1) sum += __shfl_xor_sync(0xffffffffu, sum, o);
        if (lane == 0) sts_f32(sb + OFF_WSUM + warp * 4, sum);
        bar_consumers();
        Lsum = lds_f32(sb + OFF_WSUM);
#pragma unroll
        for (int w = 1; w < 8; w++) Lsum += lds_f32(sb + OFF_WSUM + w * 4);
    }
    const float gate = lds_f32(sb + OFF_G);

    float dacc[4][4];
#pragma unroll
    for (int mt = 0; mt < 4; mt++) dacc[mt][0] = dacc[mt][1] = dacc[mt][2] = dacc[mt][3] = 0.f;
    {
        const int slot = T_WD % NSLOT;
        if (warp < 7) {
            const int line = 7 * min((li >> 1) * 8 + lr, 13) + warp;
            const uint32_t base = sb + slot * SLOT_BYTES + line * 128;
#pragma unroll
            for (int s = 0; s < 2; s++) {
                mbar_wait(bar_full + (slot * 2 + s) * 8, (T_WD / NSLOT) & 1);
                const uint32_t b0 = g == 0 ? lds_u32(sb + OFF_HS + (16 * s + 2 * t4) * 2) : 0u;
                const uint32_t b1 = g == 0 ? lds_u32(sb + OFF_HS + (16 * s + 8 + 2 * t4) * 2) : 0u;
#pragma unroll
                for (int mt = 0; mt < 4; mt++) {
                    uint32_t a0, a1, a2, a3;
                    ldsm4t(base + s * HALF_BYTES + (((2 * mt + (li & 1)) ^ (line & 7)) * 16), a0, a1, a2, a3);
                    mma16816(dacc[mt], a0, a1, a2, a3, b0, b1);
                }
            }
            const float omg = bf16r(1.f - gate);
#pragma unroll
            for (int mt = 0; mt < 4; mt++) { dacc[mt][0] *= omg; dacc[mt][1] *= omg; dacc[mt][2] *= omg; dacc[mt][3] *= omg; }
        }
        __syncwarp();
        if (lane == 0) mbar_arrive(bar_empty + slot * 8);
    }

    float oacc[4][4];
#pragma unroll
    for (int mt = 0; mt < 4; mt++) oacc[mt][0] = oacc[mt][1] = oacc[mt][2] = oacc[mt][3] = 0.f;
    {
        const uint32_t vrow = (warp * 32 + (li >> 1) * 8 + lr) * 128;
        uint32_t vch[4];
#pragma unroll
        for (int mt = 0; mt < 4; mt++) vch[mt] = vrow + (((2 * mt + (li & 1)) ^ lr) * 16);
        const uint32_t pbase = sb + OFF_P + (warp & 3) * 64 + t4 * 16;
#pragma unroll 1
        for (int t = 0; t < 16; t++) {
            const int tt = T_V0 + t, slot = tt % NSLOT;
            if (t == 12) {
                uint32_t* fp = &g_fin[(b * 64 + h * 4 + j) * 8 + (tid & 7)];
                st_relaxed(fp + (tid >> 3) * 1024, 0u);
                if (tid < 192) st_relaxed(fp + (32 + (tid >> 3)) * 1024, 0u);
            }
            const uint4 pf = lds_v4(pbase + ((2 * t + (warp >> 2) + vrot) & 31) * 256);
            mbar_wait(bar_full + (slot * 2 + (warp >> 2)) * 8, (tt / NSLOT) & 1);
            const uint32_t base = sb + slot * SLOT_BYTES;
#pragma unroll
            for (int mt = 0; mt < 4; mt++) {
                uint32_t a0, a1, a2, a3, a4, a5, a6, a7;
                ldsm4t(base + vch[mt], a0, a1, a2, a3);
                ldsm4t(base + vch[mt] + 16 * 128, a4, a5, a6, a7);
                mma16816(oacc[mt], a0, a1, a2, a3, pf.x, pf.y);
                mma16816(oacc[mt], a4, a5, a6, a7, pf.z, pf.w);
            }
            __syncwarp();
            if (lane == 0) mbar_arrive(bar_empty + slot * 8);
        }
    }

    {
        const float f = gate / Lsum;
        const float v0 = t4 == 0 ? oacc[0][0] : t4 == 1 ? oacc[1][0] : t4 == 2 ? oacc[2][0] : oacc[3][0];
        const float v1 = t4 == 0 ? oacc[0][2] : t4 == 1 ? oacc[1][2] : t4 == 2 ? oacc[2][2] : oacc[3][2];
        const uint32_t oa = sb + OFF_OBUF + warp * 144 + (16 * t4 + g) * 2;
        sts_u16(oa, bf16_bits(v0 * f));
        sts_u16(oa + 16, bf16_bits(v1 * f));
    }
    bar_consumers();
    if (warp < 7) {
        const int line = 7 * ((li >> 1) * 8 + lr) + warp;
        uint32_t wch[4];
#pragma unroll
        for (int mt = 0; mt < 4; mt++) wch[mt] = line * 128 + (((2 * mt + (li & 1)) ^ (line & 7)) * 16);
#pragma unroll
        for (int s = 0; s < 4; s++) {
            const int tt = T_WO + (s >> 1), slot = tt % NSLOT;
            uint32_t ob0, ob1;
            ldsm2(sb + OFF_OBUF + lr * 144 + (2 * s + (li & 1)) * 16, ob0, ob1);
            mbar_wait(bar_full + (slot * 2 + (s & 1)) * 8, (tt / NSLOT) & 1);
            const uint32_t base = sb + slot * SLOT_BYTES + (s & 1) * HALF_BYTES;
#pragma unroll
            for (int mt = 0; mt < 4; mt++) {
                uint32_t a0, a1, a2, a3;
                ldsm4t(base + wch[mt], a0, a1, a2, a3);
                mma16816(dacc[mt], a0, a1, a2, a3, ob0, ob1);
            }
        }
        float v[4][2];
#pragma unroll
        for (int mt = 0; mt < 4; mt++) { v[mt][0] = dacc[mt][0] + dacc[mt][1]; v[mt][1] = dacc[mt][2] + dacc[mt][3]; }
        const bool hi = (t4 & 2) != 0, lo = (t4 & 1) != 0;
        float a0 = hi ? v[2][0] : v[0][0], a1 = hi ? v[2][1] : v[0][1], a2 = hi ? v[3][0] : v[1][0], a3 = hi ? v[3][1] : v[1][1];
        const float s0 = hi ? v[0][0] : v[2][0], s1 = hi ? v[0][1] : v[2][1], s2 = hi ? v[1][0] : v[3][0], s3 = hi ? v[1][1] : v[3][1];
        a0 += __shfl_xor_sync(0xffffffffu, s0, 2); a1 += __shfl_xor_sync(0xffffffffu, s1, 2);
        a2 += __shfl_xor_sync(0xffffffffu, s2, 2); a3 += __shfl_xor_sync(0xffffffffu, s3, 2);
        float r0 = lo ? a2 : a0, r1 = lo ? a3 : a1;
        const float u0 = lo ? a0 : a2, u1 = lo ? a1 : a3;
        r0 += __shfl_xor_sync(0xffffffffu, u0, 1); r1 += __shfl_xor_sync(0xffffffffu, u1, 1);
        const int oct = 8 * warp + 2 * t4, src = h * 4 + j;
        st_relaxed(&g_fin[((oct * 2 + b) * 64 + src) * 8 + g], tag_enc(r0, tag));
        st_relaxed(&g_fin[(((oct + 1) * 2 + b) * 64 + src) * 8 + g], tag_enc(r1, tag));
    } else if (blockIdx.x < 112) {
        const uint32_t* src = &g_fin[blockIdx.x * 512 + lane * 4];
        uint4 v[4];
        int it = 0;
        for (;;) {
            bool ok = true;
#pragma unroll
            for (int i = 0; i < 4; i++) v[i] = ld_relaxed4(src + i * 128);
#pragma unroll
            for (int i = 0; i < 4; i++) ok = ok && tag_ok4(v[i], tag);
            if (poll_done(ok, it)) break;
        }
        float x0 = 0.f, x1 = 0.f, x2 = 0.f, x3 = 0.f;
#pragma unroll
        for (int i = 0; i < 4; i++) {
            x0 += tag_dec(v[i].x); x1 += tag_dec(v[i].y); x2 += tag_dec(v[i].z); x3 += tag_dec(v[i].w);
        }
#pragma unroll
        for (int o = 2; o < 32; o <<= 1) {
            x0 += __shfl_xor_sync(0xffffffffu, x0, o); x1 += __shfl_xor_sync(0xffffffffu, x1, o);
            x2 += __shfl_xor_sync(0xffffffffu, x2, o); x3 += __shfl_xor_sync(0xffffffffu, x3, o);
        }
        if (lane < 2) {
            uint2 o2 = make_uint2(pack_bf16(x0, x1), pack_bf16(x2, x3));
            *reinterpret_cast<uint2*>(p.out + (blockIdx.x & 1) * DM + (blockIdx.x >> 1) * 8 + lane * 4) = o2;
        }
        if (blockIdx.x == 0 && lane == 0) st_relaxed(&g_epoch, epoch == 2 ? 0u : epoch + 1);
    }
}

typedef CUresult (*EncodeTiledFn)(CUtensorMap*, CUtensorMapDataType, cuuint32_t, void*, const cuuint64_t*,
                                  const cuuint64_t*, const cuuint32_t*, const cuuint32_t*, CUtensorMapInterleave,
                                  CUtensorMapSwizzle, CUtensorMapL2promotion, CUtensorMapFloatOOBfill);

}

extern "C" void kernel_launch(void* const* d_in, const int* in_sizes, int n_in, void* d_out, int out_size) {
    (void)in_sizes; (void)n_in; (void)out_size;
    static EncodeTiledFn encode = nullptr;
    static uint32_t tau16 = 0;
    if (!encode) {
        int dev = 0, mclk_khz = 0, bus_bits = 0;
        cudaGetDevice(&dev);
        cudaDeviceGetAttribute(&mclk_khz, cudaDevAttrMemoryClockRate, dev);
        cudaDeviceGetAttribute(&bus_bits, cudaDevAttrGlobalMemoryBusWidth, dev);
        const double peak = 2.0 * mclk_khz * 1e3 * (bus_bits / 8.0) * 1e-9;
        tau16 = peak > 0 ? (uint32_t)(16.0 * NCTA * HALF_BYTES / (PACE * peak)) : 0u;
        cudaDriverEntryPointQueryResult qr;
        void* fn = nullptr;
        cudaGetDriverEntryPoint("cuTensorMapEncodeTiled", &fn, cudaEnableDefault, &qr);
        encode = (EncodeTiledFn)fn;
        cudaFuncSetAttribute(fused_decode_kernel, cudaFuncAttributeMaxDynamicSharedMemorySize, SMEM_BYTES);
    }
    CUtensorMap wqmap, wgmap, wumap, vmap, womap, wdmap;
    auto make_map = [&](CUtensorMap* m, void* ptr, uint64_t cols, uint64_t rows, uint32_t bcols, uint32_t brows,
                        CUtensorMapSwizzle sw) {
        cuuint64_t gdim[2] = {cols, rows};
        cuuint64_t gstr[1] = {cols * 2};
        cuuint32_t box[2] = {bcols, brows};
        cuuint32_t estr[2] = {1, 1};
        encode(m, CU_TENSOR_MAP_DATA_TYPE_BFLOAT16, 2, ptr, gdim, gstr, box, estr, CU_TENSOR_MAP_INTERLEAVE_NONE,
               sw, CU_TENSOR_MAP_L2_PROMOTION_L2_256B, CU_TENSOR_MAP_FLOAT_OOB_FILL_NONE);
    };
    make_map(&wqmap, d_in[3], NH * DH, DM, 256, 28, CU_TENSOR_MAP_SWIZZLE_NONE);
    make_map(&wgmap, d_in[6], FF, DM, 112, 56, CU_TENSOR_MAP_SWIZZLE_NONE);
    make_map(&wumap, d_in[7], FF, DM, 112, 56, CU_TENSOR_MAP_SWIZZLE_NONE);
    make_map(&vmap, d_in[2], DH, 2 * NH * SK, 64, 128, CU_TENSOR_MAP_SWIZZLE_128B);
    make_map(&womap, d_in[4], 64, NH * DH * 7, 64, 16 * 7, CU_TENSOR_MAP_SWIZZLE_128B);
    make_map(&wdmap, d_in[8], 64, FF * 7, 64, 14 * 7, CU_TENSOR_MAP_SWIZZLE_128B);
    Params p;
    p.ax = (const __nv_bfloat16*)d_in[0];
    p.kc = (const __nv_bfloat16*)d_in[1];
    p.gw = (const __nv_bfloat16*)d_in[9];
    p.out = (__nv_bfloat16*)d_out;
    p.tau16 = tau16;
    fused_decode_kernel<<<NCTA, NTHREADS, SMEM_BYTES, cudaStreamPerThread>>>(wqmap, wgmap, wumap, vmap, womap, wdmap, p);
}
```
